```python
import torch

def _softmax(x, axis=-1):
    return torch.softmax(x, dim=axis)
def _gelu(x):
    return torch.nn.functional.gelu(x, approximate="tanh")
def _silu(x):
    return torch.nn.functional.silu(x)
def _sigmoid(x):
    return torch.sigmoid(x)
def _layernorm(x, axis=-1, eps=1e-5):
    m = x.mean(dim=axis, keepdim=True)
    v = x.var(dim=axis, keepdim=True, unbiased=False)
    return (x - m) / torch.sqrt(v + eps)
def _scatter_add(tgt, idx, src, axis=0):
    return tgt.clone().index_add_(axis, idx, src)
def _segment_sum(src, seg, n):
    out = torch.zeros((n,) + src.shape[1:], dtype=src.dtype)
    return out.index_add_(0, seg, src)
def _pad(x, pw):
    flat = tuple(v for pair in reversed(pw) for v in pair)
    return torch.nn.functional.pad(x, flat)

kernel_name = 'standalone__gqa_softmax__near_ridge'

def setup_inputs():

    _w = (lambda a: (lambda t: t.to(torch.bfloat16) if t.is_floating_point() else t)(torch.as_tensor(a)))
    B, Hq, Hkv, Sq, Sk, D = 8, 16, 8, 144, 1024, 256
    return {
        "q": _w((lambda *s: torch.randn(*s, dtype=torch.bfloat16) * 0.8)(B, Hq, Sq, D)),
        "k": _w((lambda *s: torch.randn(*s, dtype=torch.bfloat16) * 0.8)(B, Hkv, Sk, D)),
        "v": _w((lambda *s: torch.randn(*s, dtype=torch.bfloat16) * 0.05)(B, Hkv, Sk, D)),
    }

def reference(q, k, v):
    B, Hq, Sq, D = q.shape
    Hkv = k.shape[1]
    rep = Hq // Hkv
    k = (lambda x, n, axis: torch.repeat_interleave(x, n, dim=axis))(k, rep, axis=1)
    v = (lambda x, n, axis: torch.repeat_interleave(x, n, dim=axis))(v, rep, axis=1)
    scale = D ** -0.5
    scores = torch.einsum("bhqd,bhkd->bhqk", q, k) * scale
    p = _softmax(scores, axis=-1)
    return torch.einsum("bhqk,bhkd->bhqd", p, v)
```

```cpp
#include <cuda_runtime.h>
#include <cuda_bf16.h>
#include <cuda.h>
#include <stdint.h>

namespace {

constexpr int SQ = 144, SK = 1024, NT = 16;
constexpr uint32_t CH_Q = 18432;
constexpr uint32_t HALF = 16384;
constexpr uint32_t OFF_Q = 0;
constexpr uint32_t OFF_P = 4 * CH_Q;
constexpr uint32_t OFF_V = OFF_P + 2 * CH_Q;
constexpr uint32_t OFF_K = OFF_V + 4 * HALF;
constexpr uint32_t OFF_SCR = OFF_K + 2 * HALF;
constexpr uint32_t OFF_BAR = OFF_SCR + CH_Q;
constexpr uint32_t OFF_M = OFF_BAR + 256;
constexpr uint32_t OFF_L = OFF_M + 576;
constexpr uint32_t SMEM_BYTES = OFF_L + 576;

constexpr uint32_t BAR_Q = OFF_BAR;
constexpr uint32_t BAR_KF = OFF_BAR + 32;
constexpr uint32_t BAR_VF = OFF_BAR + 64;
constexpr uint32_t BAR_KE = OFF_BAR + 96;
constexpr uint32_t BAR_VE = OFF_BAR + 112;
constexpr uint32_t BAR_L = OFF_BAR + 128;
constexpr uint32_t BAR_FK = OFF_BAR + 144, BAR_FV = OFF_BAR + 152;
constexpr uint32_t OFF_FLAG = OFF_BAR + 160;
constexpr int NB_FB = 0, NB_PF = 1  , NB_PE = 3, NB_WG0 = 4, NB_PA1 = 5, NB_PA3 = 6, NB_PB = 7, NB_EPI = 8  ;

#define QK_SIG 13
#define TAIL 3
#define TAILX 1
#define TAILY 0
#define PERT 0
#define STAG_D 0
#define STAG_N 64
#define STAG_MODE 0
#define GATE_K1 1
#define GATE_V0 2
#define GATE_V1 3

#define PROF_SMEM 0
#define PROF_T(i)
#define PROF_I(i)
#define PROF_G(i)
#define PROF_DUMP()

__device__ __forceinline__ void mbar_init(uint32_t a, uint32_t c) {
    asm volatile("mbarrier.init.shared::cta.b64 [%0], %1;" :: "r"(a), "r"(c) : "memory");
}
__device__ __forceinline__ void mbar_expect(uint32_t a, uint32_t bytes) {
    asm volatile("mbarrier.arrive.expect_tx.shared::cta.b64 _, [%0], %1;" :: "r"(a), "r"(bytes) : "memory");
}
__device__ __forceinline__ void mbar_wait(uint32_t a, uint32_t parity) {
    asm volatile(
        "{\n.reg .pred p;\n.reg .u32 n;\nmov.u32 n, 0;\n"
        "LW:\n"
        "mbarrier.try_wait.parity.shared::cta.b64 p, [%0], %1;\n"
        "@p bra LD;\n"
        "add.u32 n, n, 1;\n"
        "setp.lt.u32 p, n, 4000000;\n"
        "@p bra LW;\n"
        "trap;\n"
        "LD:\n}" :: "r"(a), "r"(parity) : "memory");
}
__device__ __forceinline__ void mbar_arrive(uint32_t a) {
    asm volatile("mbarrier.arrive.shared::cta.b64 _, [%0];" :: "r"(a) : "memory");
}
__device__ __forceinline__ bool elect() {
    uint32_t r;
    asm volatile("{\n.reg .pred p;\nelect.sync _|p, 0xffffffff;\nselp.u32 %0, 1, 0, p;\n}" : "=r"(r));
    return r != 0;
}
__device__ __forceinline__ void sched_fence() { asm volatile("pmevent 0;" ::: "memory"); }
__device__ __forceinline__ void mbar_arrive_cta(uint32_t a, uint32_t cta) {
    asm volatile("{\n.reg .b32 r;\nmapa.shared::cluster.u32 r, %0, %1;\nmbarrier.arrive.shared::cluster.b64 _, [r];\n}"
                 :: "r"(a), "r"(cta) : "memory");
}
__device__ __forceinline__ void tma_load(uint32_t dst, const CUtensorMap* m, uint32_t bar, int row, int chunk) {
    asm volatile("cp.async.bulk.tensor.3d.shared::cluster.global.mbarrier::complete_tx::bytes [%0], [%1, {%3, %4, %5}], [%2];"
                 :: "r"(dst), "l"(m), "r"(bar), "r"(0), "r"(row), "r"(chunk) : "memory");
}
__device__ __forceinline__ void tma_load_mc(uint32_t dst, const CUtensorMap* m, uint32_t bar, int row, int chunk) {
    asm volatile("cp.async.bulk.tensor.3d.shared::cluster.global.mbarrier::complete_tx::bytes.multicast::cluster [%0], [%1, {%3, %4, %5}], [%2], %6;"
                 :: "r"(dst), "l"(m), "r"(bar), "r"(0), "r"(row), "r"(chunk), "h"((uint16_t)3) : "memory");
}
__device__ __forceinline__ void tma_store(const CUtensorMap* m, uint32_t src, int row, int chunk) {
    asm volatile("cp.async.bulk.tensor.3d.global.shared::cta.bulk_group [%0, {%2, %3, %4}], [%1];"
                 :: "l"(m), "r"(src), "r"(0), "r"(row), "r"(chunk) : "memory");
}
__device__ __forceinline__ void nb_sync(int id, int n) { asm volatile("bar.sync %0, %1;" :: "r"(id), "r"(n) : "memory"); }
__device__ __forceinline__ void nb_arrive(int id, int n) { asm volatile("bar.arrive %0, %1;" :: "r"(id), "r"(n) : "memory"); }
__device__ __forceinline__ void wg_fence() { asm volatile("wgmma.fence.sync.aligned;" ::: "memory"); }
__device__ __forceinline__ void wg_commit() { asm volatile("wgmma.commit_group.sync.aligned;" ::: "memory"); }
template <int N> __device__ __forceinline__ void wg_wait() { asm volatile("wgmma.wait_group.sync.aligned %0;" :: "n"(N) : "memory"); }
__device__ __forceinline__ void fence_async() { asm volatile("fence.proxy.async.shared::cta;" ::: "memory"); }
__device__ __forceinline__ float ex2(float x) { float y; asm("ex2.approx.ftz.f32 %0, %1;" : "=f"(y) : "f"(x)); return y; }
__device__ __forceinline__ float rcp(float x) { float y; asm("rcp.approx.ftz.f32 %0, %1;" : "=f"(y) : "f"(x)); return y; }
__device__ __forceinline__ uint32_t pack_bf16(float lo, float hi) {
    uint32_t r; asm("cvt.rn.bf16x2.f32 %0, %1, %2;" : "=r"(r) : "f"(hi), "f"(lo)); return r;
}
__device__ __forceinline__ void stsm_t(uint32_t a, uint32_t r0, uint32_t r1, uint32_t r2, uint32_t r3) {
    asm volatile("stmatrix.sync.aligned.m8n8.x4.trans.shared.b16 [%0], {%1, %2, %3, %4};"
                 :: "r"(a), "r"(r0), "r"(r1), "r"(r2), "r"(r3) : "memory");
}
__device__ __forceinline__ float4 lds128(uint32_t a) {
    float4 v; asm volatile("ld.shared.v4.f32 {%0, %1, %2, %3}, [%4];" : "=f"(v.x), "=f"(v.y), "=f"(v.z), "=f"(v.w) : "r"(a) : "memory"); return v;
}
__device__ __forceinline__ float lds32(uint32_t a) {
    float v; asm volatile("ld.shared.f32 %0, [%1];" : "=f"(v) : "r"(a) : "memory"); return v;
}
__device__ __forceinline__ void sts32(uint32_t a, float v) { asm volatile("st.shared.f32 [%0], %1;" :: "r"(a), "f"(v) : "memory"); }
__device__ __forceinline__ void sts128(uint32_t a, float x, float y, float z, float w) {
    asm volatile("st.shared.v4.f32 [%0], {%1, %2, %3, %4};" :: "r"(a), "f"(x), "f"(y), "f"(z), "f"(w) : "memory");
}
__device__ __forceinline__ uint64_t mkdesc(uint32_t addr) {
    return (uint64_t)((addr >> 4) | (1u << 16)) | ((uint64_t)0x40000040u << 32);
}

#define WG_REGS "{%0, %1, %2, %3, %4, %5, %6, %7, %8, %9, %10, %11, %12, %13, %14, %15, %16, %17, " \
    "%18, %19, %20, %21, %22, %23, %24, %25, %26, %27, %28, %29, %30, %31, %32, %33, %34, %35, " \
    "%36, %37, %38, %39, %40, %41, %42, %43, %44, %45, %46, %47, %48, %49, %50, %51, %52, %53, " \
    "%54, %55, %56, %57, %58, %59, %60, %61, %62, %63, %64, %65, %66, %67, %68, %69, %70, %71}"
#define WG_OP8(C, d, i) C(d[i]), C(d[i + 1]), C(d[i + 2]), C(d[i + 3]), C(d[i + 4]), C(d[i + 5]), C(d[i + 6]), C(d[i + 7])
#define WG_OPS(C, d) WG_OP8(C, d, 0), WG_OP8(C, d, 8), WG_OP8(C, d, 16), WG_OP8(C, d, 24), WG_OP8(C, d, 32), \
    WG_OP8(C, d, 40), WG_OP8(C, d, 48), WG_OP8(C, d, 56), WG_OP8(C, d, 64)

template <int TA>
__device__ __forceinline__ void wgmma_acc(float (&d)[72], uint64_t da, uint64_t db) {
    asm volatile("wgmma.mma_async.sync.aligned.m64n144k16.f32.bf16.bf16 " WG_REGS ", %72, %73, 1, 1, 1, %74, 0;"
                 : WG_OPS("+f", d) : "l"(da), "l"(db), "n"(TA));
}
template <int TA>
__device__ __forceinline__ void wgmma_set(float (&d)[72], uint64_t da, uint64_t db) {
    asm volatile("wgmma.mma_async.sync.aligned.m64n144k16.f32.bf16.bf16 " WG_REGS ", %72, %73, 0, 1, 1, %74, 0;"
                 : WG_OPS("=f", d) : "l"(da), "l"(db), "n"(TA));
}
__device__ __forceinline__ void wgmma_acc_lo(float (&d)[72], uint64_t da, uint64_t db) {
    asm volatile("wgmma.mma_async.sync.aligned.m64n64k16.f32.bf16.bf16 {%0, %1, %2, %3, %4, %5, %6, %7, %8, %9, %10, %11, %12, %13, %14, %15, "
                 "%16, %17, %18, %19, %20, %21, %22, %23, %24, %25, %26, %27, %28, %29, %30, %31}, %32, %33, 1, 1, 1, 1, 0;"
                 : WG_OP8("+f", d, 0), WG_OP8("+f", d, 8), WG_OP8("+f", d, 16), WG_OP8("+f", d, 24) : "l"(da), "l"(db));
}
template <int I0, int I1> __device__ __forceinline__ void reg_fence_part(float (&d)[72]) {
#pragma unroll
    for (int i = I0; i < I1; i++) asm volatile("" : "+f"(d[i]) :: "memory");
}
template <int N> __device__ __forceinline__ void reg_fence(float (&d)[N]) {
#pragma unroll
    for (int i = 0; i < N; i++) asm volatile("" : "+f"(d[i]) :: "memory");
}

template <int K0, int K1>
__device__ __forceinline__ void issue_qk(float (&s)[72], uint32_t kaddr, uint32_t qaddr) {
    const uint64_t da = mkdesc(kaddr), db = mkdesc(qaddr);
#pragma unroll
    for (int ks = K0; ks < K1; ks++) {
        const uint64_t a = da + (uint64_t)((((ks >> 2) & 1) * 8192 + (ks & 3) * 32) >> 4);
        const uint64_t b = db + (uint64_t)(((ks >> 2) * CH_Q + (ks & 3) * 32) >> 4);
        if (ks == 0) wgmma_set<0>(s, a, b); else wgmma_acc<0>(s, a, b);
    }
}

template <int G>
__device__ __forceinline__ void softmax_group(const float* x, float (&l)[36], uint32_t paddr) {
    float p[8];
#pragma unroll
    for (int e = 0; e < 8; e++) p[e] = ex2(x[e]);
    l[4 * G + 0] += p[0]; l[4 * G + 0] += p[2];
    l[4 * G + 1] += p[1]; l[4 * G + 1] += p[3];
    l[4 * G + 2] += p[4]; l[4 * G + 2] += p[6];
    l[4 * G + 3] += p[5]; l[4 * G + 3] += p[7];
    stsm_t(paddr + G * 2048, pack_bf16(p[0], p[1]), pack_bf16(p[2], p[3]), pack_bf16(p[4], p[5]), pack_bf16(p[6], p[7]));
}
template <int G>
__device__ __forceinline__ void exact_groups(const float (&s)[72], float (&l)[36], uint32_t paddr, uint32_t maddr, float c) {
    if constexpr (G < 9) {
        const float4 m = lds128(maddr + G * 16);
        float x[8];
#pragma unroll
        for (int e = 0; e < 8; e++) x[e] = fmaf(s[8 * G + e], c, e < 4 ? (e & 1 ? m.y : m.x) : (e & 1 ? m.w : m.z));
        softmax_group<G>(x, l, paddr);
        exact_groups<G + 1>(s, l, paddr, maddr, c);
    }
}
template <int G0, int G1>
__device__ __forceinline__ void store_partial_sums(const float (&l)[36], uint32_t sb) {
    const uint32_t a = sb + OFF_SCR + ((threadIdx.x & 127) >> 2) * 576 + (threadIdx.x & 3) * 144;
#pragma unroll
    for (int i = G0; i < G1; i++) sts128(a + i * 16, l[4 * i], l[4 * i + 1], l[4 * i + 2], l[4 * i + 3]);
}
#define SM_G 3
#define SM_DC 2
__device__ __forceinline__ void softmax_main(float (&s)[72], float (&x)[16], float (&l)[36], uint32_t paddr, float nm, float c,
                                             uint32_t sb, bool last) {
    constexpr int N = 56, NG = (N + SM_G - 1) / SM_G;
    uint32_t pk[4];
#pragma unroll
    for (int g = -1; g < NG + SM_DC; g++) {
#pragma unroll
        for (int e = 0; e < SM_G; e++) {
            const int im = g * SM_G + e, ip = im + SM_G, ic = im - SM_DC * SM_G;
            if (im >= 0 && im < N) asm volatile("ex2.approx.ftz.f32 %0, %0;" : "+f"(s[im]));
            if (ip < N) asm volatile("fma.rn.f32 %0, %0, %1, %2;" : "+f"(s[ip]) : "f"(c), "f"(nm));
            if (ic >= 0 && ic < N) {
                asm volatile("add.f32 %0, %0, %1;" : "+f"(l[(ic >> 2) * 2 + (ic & 1)]) : "f"(s[ic]));
                if (ic & 1) asm volatile("cvt.rn.bf16x2.f32 %0, %1, %2;" : "=r"(pk[(ic >> 1) & 3]) : "f"(s[ic]), "f"(s[ic - 1]));
                if ((ic & 7) == 7) stsm_t(paddr + (ic >> 3) * 2048, pk[0], pk[1], pk[2], pk[3]);
            }
        }
#pragma unroll
        for (int i = 0; i < 16; i++) {
            const int st = i < 8 ? i / 4 : NG - 1 + (i - 8) / 4;
            if (st == g) asm volatile("fma.rn.f32 %0, %1, %2, %3;" : "=f"(x[i]) : "f"(s[N + i]), "f"(c), "f"(nm));
        }
        if (g < NG) sched_fence();
        if (g == (31 + SM_DC * SM_G) / SM_G && last) {
            store_partial_sums<0, 4>(l, sb);
            nb_arrive(NB_PA3, 256);
            fence_async();
            nb_arrive(NB_PA1, 256);
        }
    }
}

template <bool IS_MAX>
__device__ __forceinline__ float reduce_partials(uint32_t sb, int col) {
    const uint32_t a = sb + OFF_SCR + col * 4;
    float v[4];
#pragma unroll
    for (int r = 0; r < 32; r++) {
        const float t = lds32(a + r * 576);
        v[r & 3] = r < 4 ? t : IS_MAX ? fmaxf(v[r & 3], t) : v[r & 3] + t;
    }
    return IS_MAX ? fmaxf(fmaxf(v[0], v[1]), fmaxf(v[2], v[3])) : (v[0] + v[1]) + (v[2] + v[3]);
}
__device__ __forceinline__ void publish_rowsum(uint32_t sb, int col, float sum) {
    sts32(sb + OFF_L + col * 4, rcp(sum));
    if (!(sum >= 0x1p-50f && sum <= 0x1p60f)) sts32(sb + OFF_FLAG, 1.f);
}
__device__ __forceinline__ bool needs_exact(uint32_t sb) {
    mbar_wait(sb + BAR_L, 0);
    mbar_wait(sb + BAR_L + 8, 0);
    return __shfl_sync(0xffffffffu, lds32(sb + OFF_FLAG), 0) != 0.f;
}

template <int G0, int G1>
__device__ __forceinline__ void stage_out(const float (&o)[72], const float4 (&w)[9], uint32_t oaddr) {
#pragma unroll
    for (int i = G0; i < G1; i++)
        stsm_t(oaddr + i * 2048,
               pack_bf16(o[8 * i + 0] * w[i].x, o[8 * i + 1] * w[i].y), pack_bf16(o[8 * i + 2] * w[i].x, o[8 * i + 3] * w[i].y),
               pack_bf16(o[8 * i + 4] * w[i].z, o[8 * i + 5] * w[i].w), pack_bf16(o[8 * i + 6] * w[i].z, o[8 * i + 7] * w[i].w));
}
template <int G>
__device__ __forceinline__ void exact_out(const float (&o0)[72], const float (&o1)[72], uint32_t oaddr, uint32_t laddr) {
    if constexpr (G < 9) {
        float4 w[9];
        w[G] = lds128(laddr + G * 16);
        stage_out<G, G + 1>(o0, w, oaddr);
        stage_out<G, G + 1>(o1, w, oaddr + CH_Q);
        exact_out<G + 1>(o0, o1, oaddr, laddr);
    }
}
__device__ __forceinline__ void issue_pv_lo(float (&o)[72], uint64_t da, uint64_t db) {
    wg_fence();
#pragma unroll
    for (int kk = 0; kk < 4; kk++) wgmma_acc_lo(o, da + (uint64_t)((kk * 2048) >> 4), db + (uint64_t)((kk * 32) >> 4));
    wg_commit();
}
__device__ __forceinline__ void issue_pv(float (&o)[72], uint64_t da, uint64_t db) {
#pragma unroll
    for (int kk = 0; kk < 4; kk++) wgmma_acc<1>(o, da + (uint64_t)((kk * 2048) >> 4), db + (uint64_t)((kk * 32) >> 4));
}

__global__ void __cluster_dims__(2, 1, 1) __launch_bounds__(512, 1)
gqa_kernel(const __grid_constant__ CUtensorMap mq, const __grid_constant__ CUtensorMap mk,
           const __grid_constant__ CUtensorMap mv, const __grid_constant__ CUtensorMap mo_lo,
           const __grid_constant__ CUtensorMap mo_hi) {
    extern __shared__ __align__(1024) uint8_t smem_raw[];
    const uint32_t sb = (uint32_t)__cvta_generic_to_shared(smem_raw);
    const uint32_t rank = blockIdx.x & 1;
    const int qrow = blockIdx.x * SQ;
    const int krow = (blockIdx.x >> 1) * SK;
    if (threadIdx.x < 32) {
        if (elect()) {
            asm volatile("prefetch.tensormap [%0];" :: "l"(&mk) : "memory");
            asm volatile("prefetch.tensormap [%0];" :: "l"(&mq) : "memory");
            sched_fence();
            mbar_init(sb + BAR_KF, 1);
            mbar_init(sb + BAR_Q, 1);
            mbar_expect(sb + BAR_KF, HALF);
            tma_load(sb + OFF_P + CH_Q, &mk, sb + BAR_KF, krow, 0);
            sched_fence();
            mbar_expect(sb + BAR_Q, CH_Q);
            tma_load(sb + OFF_Q, &mq, sb + BAR_Q, qrow, 0);
            sched_fence();
            mbar_init(sb + BAR_Q + 8, 1); mbar_init(sb + BAR_KF + 8, 1); mbar_init(sb + BAR_Q + 16, 1); mbar_init(sb + BAR_Q + 24, 1);
            mbar_expect(sb + BAR_Q + 8, CH_Q);
            tma_load(sb + OFF_Q + CH_Q, &mq, sb + BAR_Q + 8, qrow, 1);
            mbar_expect(sb + BAR_KF + 8, HALF);
            tma_load(sb + OFF_K + HALF, &mk, sb + BAR_KF + 8, krow, 2);
            mbar_expect(sb + BAR_Q + 16, CH_Q);
            tma_load(sb + OFF_Q + 2 * CH_Q, &mq, sb + BAR_Q + 16, qrow, 2);
            mbar_expect(sb + BAR_Q + 24, CH_Q);
            tma_load(sb + OFF_Q + 3 * CH_Q, &mq, sb + BAR_Q + 24, qrow, 3);
            sched_fence();
#pragma unroll
            for (int i = 2; i < 8; i++) mbar_init(sb + BAR_KF + 8 * i, 1);
#pragma unroll
            for (int i = 0; i < 4; i++) mbar_init(sb + BAR_KE + 8 * i, 8);
            mbar_init(sb + BAR_L, 4); mbar_init(sb + BAR_L + 8, 4);
            mbar_init(sb + BAR_FK, 1); mbar_init(sb + BAR_FV, 1);
            sts32(sb + OFF_FLAG, 0.f);
            asm volatile("fence.mbarrier_init.release.cluster;" ::: "memory");
#pragma unroll
            for (int i = 2; i < 8; i++) mbar_expect(sb + BAR_KF + 8 * i, HALF);
            asm volatile("prefetch.tensormap [%0];" :: "l"(&mv) : "memory");
            asm volatile("prefetch.tensormap [%0];" :: "l"(&mo_lo) : "memory");
            asm volatile("prefetch.tensormap [%0];" :: "l"(&mo_hi) : "memory");
        }
        __syncwarp();
    }
    const int tid = threadIdx.x & 127, lane = threadIdx.x & 31;
    const int warp_all = __shfl_sync(0xffffffffu, threadIdx.x >> 5, 0);
    const int warp = warp_all & 3, wg = warp_all >> 2;
    asm volatile("barrier.cluster.arrive.relaxed.aligned;\nbarrier.cluster.wait.aligned;" ::: "memory");
    const uint32_t st_off = (uint32_t)(((lane >> 4) * 8 + (lane & 7)) * 128 + (((2 * warp + ((lane >> 3) & 1)) ^ (lane & 7)) << 4));

    if (wg == 3) {
        asm volatile("setmaxnreg.dec.sync.aligned.u32 24;");
        if (warp == 0) {
            uint32_t slot = 2 - 2 * rank;
#pragma unroll 1
            for (int j = 1; j < NT; j++) {
                if (j >= 2) mbar_wait(sb + BAR_KE + (j & 1) * 8, ((j - 2) >> 1) & 1);
                else mbar_wait(sb + BAR_Q + 8 * GATE_K1, 0);
                if (elect()) tma_load_mc(sb + OFF_K + slot * HALF, &mk, sb + BAR_KF + (j & 1) * 16 + rank * 8, krow + j * 64, rank * 2);
                slot = slot == 0 ? 2 : slot - 1;
            }
        } else if (warp == 1) {
#pragma unroll 1
            for (int j = 0; j < NT; j++) {
                if (j >= 2) mbar_wait(sb + BAR_VE + (j & 1) * 8, ((j - 2) >> 1) & 1);
                else mbar_wait(sb + BAR_Q + 8 * (j == 0 ? GATE_V0 : GATE_V1), 0);
                if (elect()) tma_load_mc(sb + OFF_V + ((j & 1) * 2 + rank) * HALF, &mv, sb + BAR_VF + (j & 1) * 16 + rank * 8, krow + j * 64, rank * 2);
            }
        }
        {
            const int col = warp * 36 + (lane & 15);
            const uint32_t a = sb + OFF_SCR + col * 4 + (lane >> 4) * (16 * 576);
            nb_sync(NB_PA3, 256);
            float a0 = 0.f, a1 = 0.f;
#pragma unroll
            for (int r = 0; r < 16; r += 2) { a0 += lds32(a + r * 576); a1 += lds32(a + (r + 1) * 576); }
            a0 += a1;
            a0 += __shfl_xor_sync(0xffffffffu, a0, 16);
            publish_rowsum(sb, col, a0);
            __syncwarp();
            if (lane == 0) mbar_arrive(sb + BAR_L);
        }
        if (warp < 2) {
#pragma unroll 1
            for (int i = 0; i < 4; i++) {
                const int pc = warp == 0 ? i : (0x1302 >> (4 * i)) & 3;
                const int ch = 2 * warp + (pc & 1);
                nb_sync(NB_EPI + 4 * warp + pc, 160);
                if (elect()) tma_store(pc < 2 ? &mo_lo : &mo_hi, sb + OFF_Q + ch * CH_Q + (pc >> 1) * 8192, qrow + (pc >> 1) * 64, ch);
            }
            if (elect()) asm volatile("cp.async.bulk.commit_group;\ncp.async.bulk.wait_group.read 0;" ::: "memory");
            if (needs_exact(sb)) {
                if (elect()) asm volatile("cp.async.bulk.wait_group 0;" ::: "memory");
                __syncwarp();
                nb_arrive(NB_FB, 448);
            }
        }
    } else if (wg == 0) {
        asm volatile("setmaxnreg.inc.sync.aligned.u32 136;");
        const float c = 0.0625f * 1.4426950408889634f;
        float s[72], l[36], x[16], nm = 0.f;
        {
#pragma unroll
            for (int i = 0; i < 36; i++) l[i] = 0.f;
#pragma unroll
            for (int i = 0; i < 16; i++) x[i] = -INFINITY;
            uint32_t slot = 0;
            uint32_t paddr = sb + OFF_P + st_off;
#pragma unroll 1
            for (int j = 0; j < NT; j++) {
                const uint32_t par = j & 1, ph = (j >> 1) & 1;
                const uint32_t slot_b = slot == 2 ? 0 : slot + 1;
                const uint32_t ka = sb + (j == 0 ? OFF_P + CH_Q : OFF_K + slot * HALF);
                PROF_I(8 + 4 * j);
                mbar_wait(sb + BAR_KF + par * 16, ph);
                if (j == 0) mbar_wait(sb + BAR_Q, 0);
                PROF_I(9 + 4 * j);
                wg_fence();
                issue_qk<0, 4>(s, ka, sb + OFF_Q);
                sched_fence(); softmax_group<7>(x, l, paddr); sched_fence();
                if (j == 0) mbar_wait(sb + BAR_Q + 8, 0);
                wg_fence();
                issue_qk<4, 6>(s, ka, sb + OFF_Q);
                sched_fence(); softmax_group<8>(x + 8, l, paddr); sched_fence();
                wg_fence();
                issue_qk<6, 8>(s, ka, sb + OFF_Q);
                wg_commit();
                fence_async();
                mbar_wait(sb + BAR_KF + par * 16 + 8, ph);
                if (j == 0) mbar_wait(sb + BAR_Q + 16, 0);
                wg_fence();
                issue_qk<8, 12>(s, sb + OFF_K + slot_b * HALF, sb + OFF_Q);
                wg_commit();
                wg_wait<1>();
                if (j >= 1 && j + 1 < NT && elect()) mbar_arrive_cta(sb + BAR_KE + (par ^ 1) * 8, 1);
                if (j >= 2) nb_sync(NB_PE, 384);
                if (j == 0) mbar_wait(sb + BAR_Q + 24, 0);
                wg_fence();
                issue_qk<12, QK_SIG>(s, sb + OFF_K + slot_b * HALF, sb + OFF_Q);
                wg_commit();
                issue_qk<QK_SIG, 16>(s, sb + OFF_K + slot_b * HALF, sb + OFF_Q);
                wg_commit();
                wg_wait<1>();
                if (j >= 1) nb_arrive(NB_PF, 256);
                if (j >= 1 && j < NT - 1) nb_arrive(NB_PF + 1, 256);
                PROF_I(10 + 4 * j);
                if (warp < 2 && j + 2 < NT && elect()) mbar_expect(sb + BAR_KF + par * 16 + warp * 8, HALF);
                wg_wait<0>();
                reg_fence(s);
                PROF_I(11 + 4 * j);
                if (j + 2 < NT && elect()) mbar_arrive_cta(sb + BAR_KE + par * 8, 0);
                if (j == 0) {
                    PROF_T(11);
                    float m4[4] = {s[0], s[1], s[2], s[3]};
#pragma unroll
                    for (int i = 4; i < 72; i++) m4[i & 3] = fmaxf(m4[i & 3], s[i]);
                    int mi = __float_as_int(fmaxf(fmaxf(m4[0], m4[1]), fmaxf(m4[2], m4[3])));
                    mi ^= (mi >> 31) & 0x7fffffff;
                    mi = __reduce_max_sync(0xffffffffu, mi);
                    mi ^= (mi >> 31) & 0x7fffffff;
                    sts32(sb + OFF_M + warp * 4, __int_as_float(mi));
                    nb_sync(NB_WG0, 128);
                    const float4 t = lds128(sb + OFF_M);
                    nm = -c * fmaxf(fmaxf(t.x, t.y), fmaxf(t.z, t.w));
                }
                paddr += par ? CH_Q : j ? -CH_Q : 0;
                slot = slot == 0 ? 2 : slot - 1;
                softmax_main(s, x, l, paddr, nm, c, sb, j == NT - 1);
            }
            softmax_group<7>(x, l, paddr);
            softmax_group<8>(x + 8, l, paddr);
            fence_async();
            nb_arrive(NB_PB, 256);
            sched_fence();
            PROF_T(72);
            store_partial_sums<4, 9>(l, sb);
            nb_sync(NB_WG0, 128);
            if (lane < 20) publish_rowsum(sb, warp * 36 + 16 + lane, reduce_partials<false>(sb, warp * 36 + 16 + lane));
            __syncwarp();
            if (lane == 0) mbar_arrive(sb + BAR_L + 8);
            PROF_T(73);
        }
        if (needs_exact(sb)) {
            nb_sync(NB_FB, 448);
            if (warp == 0 && elect()) {
                mbar_expect(sb + BAR_FK, 4 * CH_Q);
                for (int i = 0; i < 4; i++) tma_load(sb + OFF_Q + i * CH_Q, &mq, sb + BAR_FK, qrow, i);
            }
            mbar_wait(sb + BAR_FK, 0);
            const uint32_t maddr = sb + OFF_M + (lane & 3) * 144;
#pragma unroll 1
            for (int pass = 0; pass < 2; pass++) {
#pragma unroll
                for (int i = 0; i < 36; i++) l[i] = pass ? 0.f : -INFINITY;
#pragma unroll 1
                for (int j = 0; j < NT; j++) {
                    if (warp == 0 && elect()) {
                        mbar_expect(sb + BAR_FK, 2 * HALF);
                        tma_load(sb + OFF_K, &mk, sb + BAR_FK, krow + j * 64, 0);
                        tma_load(sb + OFF_K + HALF, &mk, sb + BAR_FK, krow + j * 64, 2);
                        if (pass) {
                            mbar_expect(sb + BAR_FV, 2 * HALF);
                            tma_load(sb + OFF_V, &mv, sb + BAR_FV, krow + j * 64, 0);
                            tma_load(sb + OFF_V + HALF, &mv, sb + BAR_FV, krow + j * 64, 2);
                        }
                    }
                    mbar_wait(sb + BAR_FK, (j & 1) ^ 1);
                    wg_fence();
                    issue_qk<0, 8>(s, sb + OFF_K, sb + OFF_Q);
                    issue_qk<8, 16>(s, sb + OFF_K + HALF, sb + OFF_Q);
                    wg_commit();
                    wg_wait<0>();
                    reg_fence(s);
                    if (pass == 0) {
#pragma unroll
                        for (int i = 0; i < 72; i++) l[(i >> 2) * 2 + (i & 1)] = fmaxf(l[(i >> 2) * 2 + (i & 1)], s[i]);
                        nb_sync(NB_WG0, 128);
                    } else {
                        exact_groups<0>(s, l, sb + OFF_P + st_off, maddr, c);
                        fence_async();
                        nb_sync(NB_PF, 384);
                        nb_sync(NB_PE, 384);
                    }
                }
                store_partial_sums<0, 9>(l, sb);
                nb_sync(NB_WG0, 128);
#pragma unroll 1
                for (int col = tid; col < SQ; col += 128) {
                    if (pass == 0) sts32(sb + OFF_M + col * 4, -c * reduce_partials<true>(sb, col));
                    else sts32(sb + OFF_L + col * 4, 1.0f / reduce_partials<false>(sb, col));
                }
                nb_sync(NB_WG0, 128);
            }
            nb_arrive(NB_PF, 384);
        }
        PROF_DUMP();
    } else {
        asm volatile("setmaxnreg.inc.sync.aligned.u32 176;");
        const uint32_t h = wg - 1;
        float o0[72], o1[72];
#pragma unroll
        for (int i = 0; i < 72; i++) { o0[i] = 0.f; o1[i] = 0.f; }
#pragma unroll 1
        for (int j = 0; j < NT - 1 - (int)h; j++) {
            const uint32_t par = j & 1;
            const uint64_t da = mkdesc(sb + OFF_V + (par * 2 + h) * HALF);
            const uint64_t db = mkdesc(sb + OFF_P + par * CH_Q);
            mbar_wait(sb + BAR_VF + par * 16 + h * 8, (j >> 1) & 1);
            PROF_I(8 + 4 * j);
            nb_sync(NB_PF + h, 256);
            wg_fence();
#pragma unroll
            for (int kk = 0; kk < 4; kk++) {
                wgmma_acc<1>(o0, da + (uint64_t)((kk * 2048) >> 4), db + (uint64_t)((kk * 32) >> 4));
                wgmma_acc<1>(o1, da + (uint64_t)((8192 + kk * 2048) >> 4), db + (uint64_t)((kk * 32) >> 4));
            }
            wg_commit();
            PROF_I(9 + 4 * j);
            if (tid == 0 && j + 2 < NT) mbar_expect(sb + BAR_VF + par * 16 + h * 8, HALF);
            wg_wait<0>();
            if (j + 2 < NT) {
                nb_arrive(NB_PE, 384);
                if (lane == 0) mbar_arrive_cta(sb + BAR_VE + par * 8, h);
            }
            PROF_T(10 + 4 * j);
        }
        const uint64_t da = mkdesc(sb + OFF_V + h * HALF), db = mkdesc(sb + OFF_P);
        constexpr uint64_t DA1 = (2 * HALF) >> 4, DB1 = CH_Q >> 4, DC1 = 8192 >> 4;
        const uint32_t laddr = sb + OFF_L + (lane & 3) * 144;
        const uint32_t oaddr = sb + OFF_Q + h * 2 * CH_Q + st_off;
        float4 w[9];
        mbar_wait(sb + BAR_VF + 16 + h * 8, 1);
        if (h == 0) {
            nb_sync(NB_PA1, 256);
            PROF_T(68);
            issue_pv_lo(o0, da + DA1, db + DB1);
            if (TAILY == 0) issue_pv_lo(o1, da + DA1 + DC1, db + DB1);
            mbar_wait(sb + BAR_L, 0);
            float4 wa[9];
#pragma unroll
            for (int i = 0; i < 4; i++) wa[i] = lds128(laddr + i * 16);
            if (TAILY == 1) issue_pv_lo(o1, da + DA1 + DC1, db + DB1);
            wg_wait<TAILY <= 1>();
            reg_fence_part<0, 32>(o0);
            stage_out<0, 4>(o0, wa, oaddr);
            if (TAILY == 2) { sched_fence(); issue_pv_lo(o1, da + DA1 + DC1, db + DB1); }
            fence_async();
            nb_arrive(NB_EPI, 160);
            if (TAILY == 3) issue_pv_lo(o1, da + DA1 + DC1, db + DB1);
            PROF_T(69);
            wg_wait<0>();
            reg_fence_part<0, 32>(o1);
            stage_out<0, 4>(o1, wa, oaddr + CH_Q);
#pragma unroll
            for (int i = 0; i < 32; i++) { asm volatile("" : "=f"(o0[i])); asm volatile("" : "=f"(o1[i])); }
            fence_async();
            nb_arrive(NB_EPI + 1, 160);
            PROF_T(70);
            nb_sync(NB_PB, 256);
        } else {
            mbar_wait(sb + BAR_VF + 8, 1);
            nb_sync(NB_PF + 1, 256);
            PROF_T(68);
            wg_fence();
            issue_pv(o0, da, db);
            wg_commit();
        }
        wg_fence();
        issue_pv(o0, da + DA1, db + DB1);
        wg_commit();
        if (h == 0 && TAIL == 0) nb_arrive(NB_PF + 1, 256);
        mbar_wait(sb + BAR_L + 8, 0);
#pragma unroll
        for (int i = 4; i < 8; i++) w[i] = lds128(laddr + i * 16);
        wg_wait<0>();
        reg_fence(o0);
        if (h == 0 && TAIL == 1) nb_arrive(NB_PF + 1, 256);
        stage_out<4, 5>(o0, w, oaddr);
        w[8] = lds128(laddr + 8 * 16);
        stage_out<5, 9>(o0, w, oaddr);
        fence_async();
        nb_arrive(NB_EPI + 4 * h + 2, 160);
        PROF_T(71);
        if (h == 0) {
            if (TAIL == 2) nb_arrive(NB_PF + 1, 256);
        } else {
            if (TAILX == 0) { wg_fence(); issue_pv(o1, da + DC1, db); wg_commit(); }
#pragma unroll
            for (int i = 0; i < 4; i++) w[i] = lds128(laddr + i * 16);
            stage_out<0, 4>(o0, w, oaddr);
            fence_async();
            nb_arrive(NB_EPI + 4, 160);
            PROF_T(70);
            if (TAILX == 1) { wg_fence(); issue_pv(o1, da + DC1, db); wg_commit(); }
        }
        wg_fence();
        issue_pv(o1, da + DA1 + DC1, db + DB1);
        wg_commit();
        if (h == 0 && TAIL == 3) nb_arrive(NB_PF + 1, 256);
        wg_wait<0>();
        reg_fence(o1);
        if (h == 0 && TAIL == 4) nb_arrive(NB_PF + 1, 256);
        stage_out<4, 9>(o1, w, oaddr + CH_Q);
        fence_async();
        nb_arrive(NB_EPI + 4 * h + 3, 160);
        PROF_T(72);
        if (h) {
            stage_out<0, 4>(o1, w, oaddr + CH_Q);
            fence_async();
            nb_arrive(NB_EPI + 5, 160);
        }
        PROF_T(73);
        if (needs_exact(sb)) {
            nb_sync(NB_FB, 448);
#pragma unroll
            for (int i = 0; i < 72; i++) { o0[i] = 0.f; o1[i] = 0.f; }
#pragma unroll 1
            for (int j = 0; j < NT; j++) {
                nb_sync(NB_PF, 384);
                mbar_wait(sb + BAR_FV, j & 1);
                wg_fence();
                issue_pv(o0, da, db);
                issue_pv(o1, da + DC1, db);
                wg_commit();
                wg_wait<0>();
                nb_sync(NB_PE, 384);
            }
            reg_fence(o0);
            reg_fence(o1);
            nb_sync(NB_PF, 384);
            exact_out<0>(o0, o1, oaddr, laddr);
            fence_async();
            nb_sync(NB_EPI + h, 128);
            if (warp == 0 && elect()) {
                for (int ch = 2 * h; ch < 2 * h + 2; ch++) {
                    tma_store(&mo_lo, sb + OFF_Q + ch * CH_Q, qrow, ch);
                    tma_store(&mo_hi, sb + OFF_Q + ch * CH_Q + 8192, qrow + 64, ch);
                }
                asm volatile("cp.async.bulk.commit_group;\ncp.async.bulk.wait_group.read 0;" ::: "memory");
            }
        }
        PROF_T(74);
        PROF_G(75);
        PROF_DUMP();
    }
}

typedef CUresult (*EncodeFn)(CUtensorMap*, CUtensorMapDataType, cuuint32_t, void*, const cuuint64_t*, const cuuint64_t*,
                             const cuuint32_t*, const cuuint32_t*, CUtensorMapInterleave, CUtensorMapSwizzle,
                             CUtensorMapL2promotion, CUtensorMapFloatOOBfill);

CUtensorMap make_map(EncodeFn enc, void* ptr, uint64_t rows, uint32_t box_rows, uint32_t box_chunks) {
    CUtensorMap m;
    cuuint64_t dims[3] = {64, rows, 4};
    cuuint64_t strides[2] = {512, 128};
    cuuint32_t box[3] = {64, box_rows, box_chunks};
    cuuint32_t es[3] = {1, 1, 1};
    enc(&m, CU_TENSOR_MAP_DATA_TYPE_BFLOAT16, 3, ptr, dims, strides, box, es, CU_TENSOR_MAP_INTERLEAVE_NONE,
        CU_TENSOR_MAP_SWIZZLE_128B, CU_TENSOR_MAP_L2_PROMOTION_L2_128B, CU_TENSOR_MAP_FLOAT_OOB_FILL_NONE);
    return m;
}

}

extern "C" void kernel_launch(void* const* d_in, const int* in_sizes, int n_in, void* d_out, int out_size) {
    static EncodeFn enc = nullptr;
    if (!enc) {
        void* fn = nullptr;
        cudaDriverEntryPointQueryResult qr;
        cudaGetDriverEntryPoint("cuTensorMapEncodeTiled", &fn, cudaEnableDefault, &qr);
        enc = (EncodeFn)fn;
        cudaFuncSetAttribute(gqa_kernel, cudaFuncAttributeMaxDynamicSharedMemorySize, SMEM_BYTES + PROF_SMEM);
    }
    const CUtensorMap mq = make_map(enc, d_in[0], 128 * SQ, SQ, 1);
    const CUtensorMap mk = make_map(enc, d_in[1], 64 * SK, 64, 2);
    const CUtensorMap mv = make_map(enc, d_in[2], 64 * SK, 64, 2);
    const CUtensorMap mo_lo = make_map(enc, d_out, 128 * SQ, 64, 1);
    const CUtensorMap mo_hi = make_map(enc, d_out, 128 * SQ, 80, 1);
    gqa_kernel<<<128, 512, SMEM_BYTES + PROF_SMEM, cudaStreamPerThread>>>(mq, mk, mv, mo_lo, mo_hi);
}
```

```cpp
#include <cuda_runtime.h>
#include <cuda_bf16.h>
#include <cuda.h>
#include <stdint.h>

namespace {

constexpr int SQ = 144, SK = 1024, NT = 16;
constexpr uint32_t CH_Q = 18432;
constexpr uint32_t HALF = 16384;
constexpr uint32_t OFF_Q = 0;
constexpr uint32_t OFF_P = 4 * CH_Q;
constexpr uint32_t OFF_V = OFF_P + 2 * CH_Q;
constexpr uint32_t OFF_K = OFF_V + 4 * HALF;
constexpr uint32_t OFF_SCR = OFF_K + 2 * HALF;
constexpr uint32_t OFF_BAR = OFF_SCR + CH_Q;
constexpr uint32_t OFF_M = OFF_BAR + 256;
constexpr uint32_t OFF_L = OFF_M + 576;
constexpr uint32_t SMEM_BYTES = OFF_L + 576;

constexpr uint32_t BAR_Q = OFF_BAR;
constexpr uint32_t BAR_KF = OFF_BAR + 32;
constexpr uint32_t BAR_VF = OFF_BAR + 64;
constexpr uint32_t BAR_KE = OFF_BAR + 96;
constexpr uint32_t BAR_VE = OFF_BAR + 112;
constexpr uint32_t BAR_L = OFF_BAR + 128;
constexpr uint32_t BAR_FK = OFF_BAR + 144, BAR_FV = OFF_BAR + 152;
constexpr uint32_t OFF_FLAG = OFF_BAR + 160;
constexpr int NB_FB = 0, NB_PF = 1  , NB_PE = 3, NB_WG0 = 4, NB_PA1 = 5, NB_PA3 = 6, NB_PB = 7, NB_EPI = 8  ;

constexpr int QK_SIG = 13;
constexpr int SM_G = 3, SM_DC = 2;
constexpr uint32_t T_Q1 = 1700, T_K0B = 2900, T_Q2 = 3500, T_Q3 = 4800;
constexpr uint32_t T_KV = 6300, T_HALF = 540;
constexpr int T_TILES = 5;

__device__ __forceinline__ void mbar_init(uint32_t a, uint32_t c) {
    asm volatile("mbarrier.init.shared::cta.b64 [%0], %1;" :: "r"(a), "r"(c) : "memory");
}
__device__ __forceinline__ void mbar_expect(uint32_t a, uint32_t bytes) {
    asm volatile("mbarrier.arrive.expect_tx.shared::cta.b64 _, [%0], %1;" :: "r"(a), "r"(bytes) : "memory");
}
__device__ __forceinline__ void mbar_wait(uint32_t a, uint32_t parity) {
    asm volatile(
        "{\n.reg .pred p;\n.reg .u32 n;\nmov.u32 n, 0;\n"
        "LW:\n"
        "mbarrier.try_wait.parity.shared::cta.b64 p, [%0], %1;\n"
        "@p bra LD;\n"
        "add.u32 n, n, 1;\n"
        "setp.lt.u32 p, n, 4000000;\n"
        "@p bra LW;\n"
        "trap;\n"
        "LD:\n}" :: "r"(a), "r"(parity) : "memory");
}
__device__ __forceinline__ uint32_t now_clk() { uint32_t t; asm volatile("mov.u32 %0, %%clock;" : "=r"(t)); return t; }
__device__ __forceinline__ void wait_until(uint32_t t0, uint32_t dt, uint32_t pace) {
    dt = dt * pace >> 8;
    for (int i = 0; i < 100000 && (int)(now_clk() - t0 - dt) < 0; i++) {}
}
__device__ __forceinline__ void mbar_arrive(uint32_t a) {
    asm volatile("mbarrier.arrive.shared::cta.b64 _, [%0];" :: "r"(a) : "memory");
}
__device__ __forceinline__ bool elect() {
    uint32_t r;
    asm volatile("{\n.reg .pred p;\nelect.sync _|p, 0xffffffff;\nselp.u32 %0, 1, 0, p;\n}" : "=r"(r));
    return r != 0;
}
__device__ __forceinline__ void sched_fence() { asm volatile("pmevent 0;" ::: "memory"); }
__device__ __forceinline__ void mbar_arrive_cta(uint32_t a, uint32_t cta) {
    asm volatile("{\n.reg .b32 r;\nmapa.shared::cluster.u32 r, %0, %1;\nmbarrier.arrive.shared::cluster.b64 _, [r];\n}"
                 :: "r"(a), "r"(cta) : "memory");
}
__device__ __forceinline__ void tma_load(uint32_t dst, const CUtensorMap* m, uint32_t bar, int row, int chunk) {
    asm volatile("cp.async.bulk.tensor.3d.shared::cluster.global.mbarrier::complete_tx::bytes [%0], [%1, {%3, %4, %5}], [%2];"
                 :: "r"(dst), "l"(m), "r"(bar), "r"(0), "r"(row), "r"(chunk) : "memory");
}
__device__ __forceinline__ void tma_load_mc(uint32_t dst, const CUtensorMap* m, uint32_t bar, int row, int chunk) {
    asm volatile("cp.async.bulk.tensor.3d.shared::cluster.global.mbarrier::complete_tx::bytes.multicast::cluster [%0], [%1, {%3, %4, %5}], [%2], %6;"
                 :: "r"(dst), "l"(m), "r"(bar), "r"(0), "r"(row), "r"(chunk), "h"((uint16_t)3) : "memory");
}
__device__ __forceinline__ void tma_prefetch(const CUtensorMap* m, int row, int chunk) {
    asm volatile("cp.async.bulk.prefetch.tensor.3d.L2.global [%0, {%1, %2, %3}];" :: "l"(m), "r"(0), "r"(row), "r"(chunk) : "memory");
}
__device__ __forceinline__ void tma_store(const CUtensorMap* m, uint32_t src, int row, int chunk) {
    asm volatile("cp.async.bulk.tensor.3d.global.shared::cta.bulk_group [%0, {%2, %3, %4}], [%1];"
                 :: "l"(m), "r"(src), "r"(0), "r"(row), "r"(chunk) : "memory");
}
__device__ __forceinline__ void nb_sync(int id, int n) { asm volatile("bar.sync %0, %1;" :: "r"(id), "r"(n) : "memory"); }
__device__ __forceinline__ void nb_arrive(int id, int n) { asm volatile("bar.arrive %0, %1;" :: "r"(id), "r"(n) : "memory"); }
__device__ __forceinline__ void wg_fence() { asm volatile("wgmma.fence.sync.aligned;" ::: "memory"); }
__device__ __forceinline__ void wg_commit() { asm volatile("wgmma.commit_group.sync.aligned;" ::: "memory"); }
template <int N> __device__ __forceinline__ void wg_wait() { asm volatile("wgmma.wait_group.sync.aligned %0;" :: "n"(N) : "memory"); }
__device__ __forceinline__ void fence_async() { asm volatile("fence.proxy.async.shared::cta;" ::: "memory"); }
__device__ __forceinline__ float ex2(float x) { float y; asm("ex2.approx.ftz.f32 %0, %1;" : "=f"(y) : "f"(x)); return y; }
__device__ __forceinline__ float rcp(float x) { float y; asm("rcp.approx.ftz.f32 %0, %1;" : "=f"(y) : "f"(x)); return y; }
__device__ __forceinline__ uint32_t pack_bf16(float lo, float hi) {
    uint32_t r; asm("cvt.rn.bf16x2.f32 %0, %1, %2;" : "=r"(r) : "f"(hi), "f"(lo)); return r;
}
__device__ __forceinline__ void stsm_t(uint32_t a, uint32_t r0, uint32_t r1, uint32_t r2, uint32_t r3) {
    asm volatile("stmatrix.sync.aligned.m8n8.x4.trans.shared.b16 [%0], {%1, %2, %3, %4};"
                 :: "r"(a), "r"(r0), "r"(r1), "r"(r2), "r"(r3) : "memory");
}
__device__ __forceinline__ float4 lds128(uint32_t a) {
    float4 v; asm volatile("ld.shared.v4.f32 {%0, %1, %2, %3}, [%4];" : "=f"(v.x), "=f"(v.y), "=f"(v.z), "=f"(v.w) : "r"(a) : "memory"); return v;
}
__device__ __forceinline__ float lds32(uint32_t a) {
    float v; asm volatile("ld.shared.f32 %0, [%1];" : "=f"(v) : "r"(a) : "memory"); return v;
}
__device__ __forceinline__ void sts32(uint32_t a, float v) { asm volatile("st.shared.f32 [%0], %1;" :: "r"(a), "f"(v) : "memory"); }
__device__ __forceinline__ void sts128(uint32_t a, float x, float y, float z, float w) {
    asm volatile("st.shared.v4.f32 [%0], {%1, %2, %3, %4};" :: "r"(a), "f"(x), "f"(y), "f"(z), "f"(w) : "memory");
}
__device__ __forceinline__ uint64_t mkdesc(uint32_t addr) {
    return (uint64_t)(((addr & 0x3FFFF) >> 4) | (1u << 16)) | ((uint64_t)0x40000040u << 32);
}

#define WG_REGS "{%0, %1, %2, %3, %4, %5, %6, %7, %8, %9, %10, %11, %12, %13, %14, %15, %16, %17, " \
    "%18, %19, %20, %21, %22, %23, %24, %25, %26, %27, %28, %29, %30, %31, %32, %33, %34, %35, " \
    "%36, %37, %38, %39, %40, %41, %42, %43, %44, %45, %46, %47, %48, %49, %50, %51, %52, %53, " \
    "%54, %55, %56, %57, %58, %59, %60, %61, %62, %63, %64, %65, %66, %67, %68, %69, %70, %71}"
#define WG_OP8(C, d, i) C(d[i]), C(d[i + 1]), C(d[i + 2]), C(d[i + 3]), C(d[i + 4]), C(d[i + 5]), C(d[i + 6]), C(d[i + 7])
#define WG_OPS(C, d) WG_OP8(C, d, 0), WG_OP8(C, d, 8), WG_OP8(C, d, 16), WG_OP8(C, d, 24), WG_OP8(C, d, 32), \
    WG_OP8(C, d, 40), WG_OP8(C, d, 48), WG_OP8(C, d, 56), WG_OP8(C, d, 64)

template <int TA>
__device__ __forceinline__ void wgmma_acc(float (&d)[72], uint64_t da, uint64_t db) {
    asm volatile("wgmma.mma_async.sync.aligned.m64n144k16.f32.bf16.bf16 " WG_REGS ", %72, %73, 1, 1, 1, %74, 0;"
                 : WG_OPS("+f", d) : "l"(da), "l"(db), "n"(TA));
}
template <int TA>
__device__ __forceinline__ void wgmma_set(float (&d)[72], uint64_t da, uint64_t db) {
    asm volatile("wgmma.mma_async.sync.aligned.m64n144k16.f32.bf16.bf16 " WG_REGS ", %72, %73, 0, 1, 1, %74, 0;"
                 : WG_OPS("=f", d) : "l"(da), "l"(db), "n"(TA));
}
__device__ __forceinline__ void wgmma_acc_lo(float (&d)[72], uint64_t da, uint64_t db) {
    asm volatile("wgmma.mma_async.sync.aligned.m64n64k16.f32.bf16.bf16 {%0, %1, %2, %3, %4, %5, %6, %7, %8, %9, %10, %11, %12, %13, %14, %15, "
                 "%16, %17, %18, %19, %20, %21, %22, %23, %24, %25, %26, %27, %28, %29, %30, %31}, %32, %33, 1, 1, 1, 1, 0;"
                 : WG_OP8("+f", d, 0), WG_OP8("+f", d, 8), WG_OP8("+f", d, 16), WG_OP8("+f", d, 24) : "l"(da), "l"(db));
}
template <int I0, int I1> __device__ __forceinline__ void reg_fence_part(float (&d)[72]) {
#pragma unroll
    for (int i = I0; i < I1; i++) asm volatile("" : "+f"(d[i]) :: "memory");
}
template <int N> __device__ __forceinline__ void reg_fence(float (&d)[N]) {
#pragma unroll
    for (int i = 0; i < N; i++) asm volatile("" : "+f"(d[i]) :: "memory");
}

template <int K0, int K1>
__device__ __forceinline__ void issue_qk(float (&s)[72], uint32_t kaddr, uint32_t qaddr) {
    const uint64_t da = mkdesc(kaddr), db = mkdesc(qaddr);
#pragma unroll
    for (int ks = K0; ks < K1; ks++) {
        const uint64_t a = da + (uint64_t)((((ks >> 2) & 1) * 8192 + (ks & 3) * 32) >> 4);
        const uint64_t b = db + (uint64_t)(((ks >> 2) * CH_Q + (ks & 3) * 32) >> 4);
        if (ks == 0) wgmma_set<0>(s, a, b); else wgmma_acc<0>(s, a, b);
    }
}

template <int G>
__device__ __forceinline__ void softmax_group(const float* x, float (&l)[36], uint32_t paddr) {
    float p[8];
#pragma unroll
    for (int e = 0; e < 8; e++) p[e] = ex2(x[e]);
    l[4 * G + 0] += p[0]; l[4 * G + 0] += p[2];
    l[4 * G + 1] += p[1]; l[4 * G + 1] += p[3];
    l[4 * G + 2] += p[4]; l[4 * G + 2] += p[6];
    l[4 * G + 3] += p[5]; l[4 * G + 3] += p[7];
    stsm_t(paddr + G * 2048, pack_bf16(p[0], p[1]), pack_bf16(p[2], p[3]), pack_bf16(p[4], p[5]), pack_bf16(p[6], p[7]));
}
__device__ __forceinline__ float tile_max(const float (&s)[72], uint32_t sb, int warp) {
    float m4[4] = {s[0], s[1], s[2], s[3]};
#pragma unroll
    for (int i = 4; i < 72; i++) m4[i & 3] = fmaxf(m4[i & 3], s[i]);
    int mi = __float_as_int(fmaxf(fmaxf(m4[0], m4[1]), fmaxf(m4[2], m4[3])));
    mi ^= (mi >> 31) & 0x7fffffff;
    mi = __reduce_max_sync(0xffffffffu, mi);
    mi ^= (mi >> 31) & 0x7fffffff;
    sts32(sb + OFF_M + warp * 4, __int_as_float(mi));
    nb_sync(NB_WG0, 128);
    const float4 t = lds128(sb + OFF_M);
    return fmaxf(fmaxf(t.x, t.y), fmaxf(t.z, t.w));
}
template <int G>
__device__ __forceinline__ void exact_groups(const float (&s)[72], float (&l)[36], uint32_t paddr, uint32_t maddr, float c) {
    if constexpr (G < 9) {
        const float4 m = lds128(maddr + G * 16);
        float x[8];
#pragma unroll
        for (int e = 0; e < 8; e++) x[e] = (s[8 * G + e] - (e < 4 ? (e & 1 ? m.y : m.x) : (e & 1 ? m.w : m.z))) * c;
        softmax_group<G>(x, l, paddr);
        exact_groups<G + 1>(s, l, paddr, maddr, c);
    }
}
template <int G0, int G1>
__device__ __forceinline__ void store_partial_sums(const float (&l)[36], uint32_t sb) {
    const uint32_t a = sb + OFF_SCR + ((threadIdx.x & 127) >> 2) * 576 + (threadIdx.x & 3) * 144;
#pragma unroll
    for (int i = G0; i < G1; i++) sts128(a + i * 16, l[4 * i], l[4 * i + 1], l[4 * i + 2], l[4 * i + 3]);
}
__device__ __forceinline__ void softmax_main(float (&s)[72], float (&x)[16], float (&l)[36], uint32_t paddr, float nm, float c,
                                             uint32_t sb, bool last) {
    constexpr int N = 56, NG = (N + SM_G - 1) / SM_G;
    uint32_t pk[4];
#pragma unroll
    for (int g = -1; g < NG + SM_DC; g++) {
#pragma unroll
        for (int e = 0; e < SM_G; e++) {
            const int im = g * SM_G + e, ip = im + SM_G, ic = im - SM_DC * SM_G;
            if (im >= 0 && im < N) asm volatile("ex2.approx.ftz.f32 %0, %0;" : "+f"(s[im]));
            if (ip < N) asm volatile("fma.rn.f32 %0, %0, %1, %2;" : "+f"(s[ip]) : "f"(c), "f"(nm));
            if (ic >= 0 && ic < N) {
                asm volatile("add.f32 %0, %0, %1;" : "+f"(l[(ic >> 2) * 2 + (ic & 1)]) : "f"(s[ic]));
                if (ic & 1) asm volatile("cvt.rn.bf16x2.f32 %0, %1, %2;" : "=r"(pk[(ic >> 1) & 3]) : "f"(s[ic]), "f"(s[ic - 1]));
                if ((ic & 7) == 7) stsm_t(paddr + (ic >> 3) * 2048, pk[0], pk[1], pk[2], pk[3]);
            }
        }
#pragma unroll
        for (int i = 0; i < 16; i++) {
            const int st = i < 8 ? i / 4 : NG - 1 + (i - 8) / 4;
            if (st == g) asm volatile("fma.rn.f32 %0, %1, %2, %3;" : "=f"(x[i]) : "f"(s[N + i]), "f"(c), "f"(nm));
        }
        if (g < NG) sched_fence();
        if (g == (31 + SM_DC * SM_G) / SM_G && last) {
            store_partial_sums<0, 4>(l, sb);
            nb_arrive(NB_PA3, 256);
            fence_async();
            nb_arrive(NB_PA1, 256);
        }
    }
}

template <bool IS_MAX>
__device__ __forceinline__ float reduce_partials(uint32_t sb, int col) {
    const uint32_t a = sb + OFF_SCR + col * 4;
    float v[4];
#pragma unroll
    for (int r = 0; r < 32; r++) {
        const float t = lds32(a + r * 576);
        v[r & 3] = r < 4 ? t : IS_MAX ? fmaxf(v[r & 3], t) : v[r & 3] + t;
    }
    return IS_MAX ? fmaxf(fmaxf(v[0], v[1]), fmaxf(v[2], v[3])) : (v[0] + v[1]) + (v[2] + v[3]);
}
__device__ __forceinline__ void publish_rowsum(uint32_t sb, int col, float sum) {
    sts32(sb + OFF_L + col * 4, rcp(sum));
    if (!(sum >= 0x1p-48f && sum <= 0x1p48f)) sts32(sb + OFF_FLAG, 1.f);
}
__device__ __forceinline__ bool needs_exact(uint32_t sb) {
    mbar_wait(sb + BAR_L, 0);
    mbar_wait(sb + BAR_L + 8, 0);
    return __shfl_sync(0xffffffffu, lds32(sb + OFF_FLAG), 0) != 0.f;
}

template <int G0, int G1>
__device__ __forceinline__ void stage_out(const float (&o)[72], const float4 (&w)[9], uint32_t oaddr) {
#pragma unroll
    for (int i = G0; i < G1; i++)
        stsm_t(oaddr + i * 2048,
               pack_bf16(o[8 * i + 0] * w[i].x, o[8 * i + 1] * w[i].y), pack_bf16(o[8 * i + 2] * w[i].x, o[8 * i + 3] * w[i].y),
               pack_bf16(o[8 * i + 4] * w[i].z, o[8 * i + 5] * w[i].w), pack_bf16(o[8 * i + 6] * w[i].z, o[8 * i + 7] * w[i].w));
}
template <int G>
__device__ __forceinline__ void exact_out(const float (&o0)[72], const float (&o1)[72], uint32_t oaddr, uint32_t laddr) {
    if constexpr (G < 9) {
        float4 w[9];
        w[G] = lds128(laddr + G * 16);
        stage_out<G, G + 1>(o0, w, oaddr);
        stage_out<G, G + 1>(o1, w, oaddr + CH_Q);
        exact_out<G + 1>(o0, o1, oaddr, laddr);
    }
}
__device__ __forceinline__ void issue_pv_lo(float (&o)[72], uint64_t da, uint64_t db) {
    wg_fence();
#pragma unroll
    for (int kk = 0; kk < 4; kk++) wgmma_acc_lo(o, da + (uint64_t)((kk * 2048) >> 4), db + (uint64_t)((kk * 32) >> 4));
    wg_commit();
}
__device__ __forceinline__ void issue_pv(float (&o)[72], uint64_t da, uint64_t db) {
#pragma unroll
    for (int kk = 0; kk < 4; kk++) wgmma_acc<1>(o, da + (uint64_t)((kk * 2048) >> 4), db + (uint64_t)((kk * 32) >> 4));
}

__global__ void __cluster_dims__(2, 1, 1) __launch_bounds__(512, 1)
gqa_kernel(const __grid_constant__ CUtensorMap mq, const __grid_constant__ CUtensorMap mk,
           const __grid_constant__ CUtensorMap mv, const __grid_constant__ CUtensorMap mo_lo,
           const __grid_constant__ CUtensorMap mo_hi, const uint32_t pace) {
    extern __shared__ __align__(1024) uint8_t smem_raw[];
    const uint32_t sb = (uint32_t)__cvta_generic_to_shared(smem_raw);
    const uint32_t rank = blockIdx.x & 1;
    const int qrow = blockIdx.x * SQ;
    const int krow = (blockIdx.x >> 1) * SK;
    const uint32_t t_start = now_clk();
    asm volatile("prefetch.tensormap [%0];" :: "l"(&mk) : "memory");
    asm volatile("prefetch.tensormap [%0];" :: "l"(&mq) : "memory");
    if (threadIdx.x < 32) {
        if (elect()) {
            mbar_init(sb + BAR_KF, 1);
            mbar_init(sb + BAR_Q, 1);
            mbar_expect(sb + BAR_KF, HALF);
            tma_load(sb + OFF_P + CH_Q, &mk, sb + BAR_KF, krow, 0);
            sched_fence();
            mbar_expect(sb + BAR_Q, CH_Q);
            tma_load(sb + OFF_Q, &mq, sb + BAR_Q, qrow, 0);
            sched_fence();
#pragma unroll
            for (int i = 1; i < 4; i++) mbar_init(sb + BAR_Q + 8 * i, 1);
#pragma unroll
            for (int i = 1; i < 8; i++) mbar_init(sb + BAR_KF + 8 * i, 1);
#pragma unroll
            for (int i = 0; i < 4; i++) mbar_init(sb + BAR_KE + 8 * i, 8);
            mbar_init(sb + BAR_L, 128); mbar_init(sb + BAR_L + 8, 128);
            mbar_init(sb + BAR_FK, 1); mbar_init(sb + BAR_FV, 1);
            sts32(sb + OFF_FLAG, 0.f);
            asm volatile("fence.mbarrier_init.release.cluster;" ::: "memory");
#pragma unroll
            for (int i = 1; i < 4; i++) mbar_expect(sb + BAR_Q + 8 * i, CH_Q);
#pragma unroll
            for (int i = 1; i < 8; i++) mbar_expect(sb + BAR_KF + 8 * i, HALF);
            asm volatile("prefetch.tensormap [%0];" :: "l"(&mv) : "memory");
            asm volatile("prefetch.tensormap [%0];" :: "l"(&mo_lo) : "memory");
            asm volatile("prefetch.tensormap [%0];" :: "l"(&mo_hi) : "memory");
        }
        __syncwarp();
    }
    const int tid = threadIdx.x & 127, lane = threadIdx.x & 31;
    const int warp_all = __shfl_sync(0xffffffffu, threadIdx.x >> 5, 0);
    const int warp = warp_all & 3, wg = warp_all >> 2;
    asm volatile("barrier.cluster.arrive.relaxed.aligned;\nbarrier.cluster.wait.aligned;" ::: "memory");
    const uint32_t st_off = (uint32_t)(((lane >> 4) * 8 + (lane & 7)) * 128 + (((2 * warp + ((lane >> 3) & 1)) ^ (lane & 7)) << 4));

    if (wg == 3) {
        asm volatile("setmaxnreg.dec.sync.aligned.u32 24;");
        if (warp == 0) {
            wait_until(t_start, T_Q1, pace);
            if (elect()) tma_load(sb + OFF_Q + CH_Q, &mq, sb + BAR_Q + 8, qrow, 1);
            wait_until(t_start, T_K0B, pace);
            if (elect()) tma_load(sb + OFF_K + HALF, &mk, sb + BAR_KF + 8, krow, 2);
            wait_until(t_start, T_Q2, pace);
            if (elect()) tma_load(sb + OFF_Q + 2 * CH_Q, &mq, sb + BAR_Q + 16, qrow, 2);
            wait_until(t_start, T_Q3, pace);
            if (elect()) tma_load(sb + OFF_Q + 3 * CH_Q, &mq, sb + BAR_Q + 24, qrow, 3);
            uint32_t slot = 2 - 2 * rank;
#pragma unroll 1
            for (int j = 1; j < NT; j++) {
                if (j >= 2) mbar_wait(sb + BAR_KE + (j & 1) * 8, ((j - 2) >> 1) & 1);
                if (j <= T_TILES) wait_until(t_start, T_KV + (4 * j - 4 + rank) * T_HALF, pace);
                if (elect())
                    tma_load_mc(sb + OFF_K + slot * HALF, &mk, sb + BAR_KF + (j & 1) * 16 + rank * 8, krow + j * 64, rank * 2);
                if (rank == 0 && j >= 2) {
                    if (j <= T_TILES) wait_until(t_start, T_KV + (4 * j - 3) * T_HALF, pace);
                    if (elect()) tma_prefetch(&mk, krow + j * 64, 2);
                }
                slot = slot == 0 ? 2 : slot - 1;
            }
        } else if (warp == 1) {
#pragma unroll 1
            for (int j = 0; j < NT; j++) {
                if (j >= 2) mbar_wait(sb + BAR_VE + (j & 1) * 8, ((j - 2) >> 1) & 1);
                if (j < T_TILES) wait_until(t_start, T_KV + (4 * j + 2 + rank) * T_HALF, pace);
                if (elect())
                    tma_load_mc(sb + OFF_V + ((j & 1) * 2 + rank) * HALF, &mv, sb + BAR_VF + (j & 1) * 16 + rank * 8, krow + j * 64, rank * 2);
            }
        }
        {
            const int col = warp * 36 + (lane & 15);
            const uint32_t a = sb + OFF_SCR + col * 4 + (lane >> 4) * 576;
            nb_sync(NB_PA3, 256);
            float a0 = 0.f, a1 = 0.f;
#pragma unroll
            for (int r = 0; r < 32; r += 4) { a0 += lds32(a + r * 576); a1 += lds32(a + (r + 2) * 576); }
            a0 += a1;
            a0 += __shfl_xor_sync(0xffffffffu, a0, 16);
            publish_rowsum(sb, col, a0);
            mbar_arrive(sb + BAR_L);
        }
        if (warp < 2) {
#pragma unroll 1
            for (int i = 0; i < 4; i++) {
                const int pc = warp == 0 ? i : (0x1302 >> (4 * i)) & 3;
                const int ch = 2 * warp + (pc & 1);
                nb_sync(NB_EPI + 4 * warp + pc, 160);
                if (elect()) tma_store(pc < 2 ? &mo_lo : &mo_hi, sb + OFF_Q + ch * CH_Q + (pc >> 1) * 8192, qrow + (pc >> 1) * 64, ch);
            }
            if (elect()) asm volatile("cp.async.bulk.commit_group;" ::: "memory");
            if (needs_exact(sb)) {
                if (elect()) asm volatile("cp.async.bulk.wait_group 0;" ::: "memory");
                __syncwarp();
                nb_arrive(NB_FB, 448);
            } else {
                if (elect()) asm volatile("cp.async.bulk.wait_group.read 0;" ::: "memory");
            }
        }
    } else if (wg == 0) {
        asm volatile("setmaxnreg.inc.sync.aligned.u32 136;");
        const float c = 0.0625f * 1.4426950408889634f;
        float s[72], l[36], x[16], nm = 0.f;
        {
#pragma unroll
            for (int i = 0; i < 36; i++) l[i] = 0.f;
#pragma unroll
            for (int i = 0; i < 16; i++) x[i] = -INFINITY;
            uint32_t slot = 0;
            uint32_t paddr = sb + OFF_P + st_off;
#pragma unroll 1
            for (int j = 0; j < NT; j++) {
                const uint32_t par = j & 1, ph = (j >> 1) & 1;
                const uint32_t slot_b = slot == 2 ? 0 : slot + 1;
                const uint32_t ka = sb + (j == 0 ? OFF_P + CH_Q : OFF_K + slot * HALF);
                mbar_wait(sb + BAR_KF + par * 16, ph);
                if (j == 0) mbar_wait(sb + BAR_Q, 0);
                wg_fence();
                issue_qk<0, 4>(s, ka, sb + OFF_Q);
                sched_fence(); softmax_group<7>(x, l, paddr); sched_fence();
                if (j == 0) mbar_wait(sb + BAR_Q + 8, 0);
                wg_fence();
                issue_qk<4, 6>(s, ka, sb + OFF_Q);
                sched_fence(); softmax_group<8>(x + 8, l, paddr); sched_fence();
                wg_fence();
                issue_qk<6, 8>(s, ka, sb + OFF_Q);
                wg_commit();
                fence_async();
                if (j == 0) {
                    wg_wait<0>();
                    reg_fence(s);
                    nm = -1.25f * c * tile_max(s, sb, warp);
                }
                mbar_wait(sb + BAR_KF + par * 16 + 8, ph);
                if (j == 0) mbar_wait(sb + BAR_Q + 16, 0);
                wg_fence();
                issue_qk<8, 12>(s, sb + OFF_K + slot_b * HALF, sb + OFF_Q);
                wg_commit();
                wg_wait<1>();
                if (j >= 1 && j + 1 < NT && elect()) mbar_arrive_cta(sb + BAR_KE + (par ^ 1) * 8, 1);
                if (j >= 2) nb_sync(NB_PE, 384);
                if (j == 0) mbar_wait(sb + BAR_Q + 24, 0);
                wg_fence();
                issue_qk<12, QK_SIG>(s, sb + OFF_K + slot_b * HALF, sb + OFF_Q);
                wg_commit();
                issue_qk<QK_SIG, 16>(s, sb + OFF_K + slot_b * HALF, sb + OFF_Q);
                wg_commit();
                wg_wait<1>();
                if (j >= 1) nb_arrive(NB_PF, 256);
                if (j >= 1 && j < NT - 1) nb_arrive(NB_PF + 1, 256);
                if (warp < 2 && j + 2 < NT && elect()) mbar_expect(sb + BAR_KF + par * 16 + warp * 8, HALF);
                wg_wait<0>();
                reg_fence(s);
                if (j + 2 < NT && elect()) mbar_arrive_cta(sb + BAR_KE + par * 8, 0);
                paddr += par ? CH_Q : j ? -CH_Q : 0;
                slot = slot == 0 ? 2 : slot - 1;
                softmax_main(s, x, l, paddr, nm, c, sb, j == NT - 1);
            }
            softmax_group<7>(x, l, paddr);
            softmax_group<8>(x + 8, l, paddr);
            fence_async();
            nb_arrive(NB_PB, 256);
            sched_fence();
            store_partial_sums<4, 9>(l, sb);
            nb_sync(NB_WG0, 128);
            if (lane < 20) publish_rowsum(sb, warp * 36 + 16 + lane, reduce_partials<false>(sb, warp * 36 + 16 + lane));
            mbar_arrive(sb + BAR_L + 8);
        }
        if (needs_exact(sb)) {
            nb_sync(NB_FB, 448);
            if (warp == 0 && elect()) {
                mbar_expect(sb + BAR_FK, 4 * CH_Q);
                for (int i = 0; i < 4; i++) tma_load(sb + OFF_Q + i * CH_Q, &mq, sb + BAR_FK, qrow, i);
            }
            mbar_wait(sb + BAR_FK, 0);
            nb_sync(NB_WG0, 128);
            const uint32_t maddr = sb + OFF_M + (lane & 3) * 144;
#pragma unroll 1
            for (int pass = 0; pass < 2; pass++) {
#pragma unroll
                for (int i = 0; i < 36; i++) l[i] = pass ? 0.f : -INFINITY;
#pragma unroll 1
                for (int j = 0; j < NT; j++) {
                    if (warp == 0 && elect()) {
                        mbar_expect(sb + BAR_FK, 2 * HALF);
                        tma_load(sb + OFF_K, &mk, sb + BAR_FK, krow + j * 64, 0);
                        tma_load(sb + OFF_K + HALF, &mk, sb + BAR_FK, krow + j * 64, 2);
                        if (pass) {
                            mbar_expect(sb + BAR_FV, 2 * HALF);
                            tma_load(sb + OFF_V, &mv, sb + BAR_FV, krow + j * 64, 0);
                            tma_load(sb + OFF_V + HALF, &mv, sb + BAR_FV, krow + j * 64, 2);
                        }
                    }
                    mbar_wait(sb + BAR_FK, (j & 1) ^ 1);
                    wg_fence();
                    issue_qk<0, 8>(s, sb + OFF_K, sb + OFF_Q);
                    issue_qk<8, 16>(s, sb + OFF_K + HALF, sb + OFF_Q);
                    wg_commit();
                    wg_wait<0>();
                    reg_fence(s);
                    if (pass == 0) {
#pragma unroll
                        for (int i = 0; i < 72; i++) l[(i >> 2) * 2 + (i & 1)] = fmaxf(l[(i >> 2) * 2 + (i & 1)], s[i]);
                        nb_sync(NB_WG0, 128);
                    } else {
                        exact_groups<0>(s, l, sb + OFF_P + st_off, maddr, c);
                        fence_async();
                        nb_sync(NB_PF, 384);
                        nb_sync(NB_PE, 384);
                    }
                }
                store_partial_sums<0, 9>(l, sb);
                nb_sync(NB_WG0, 128);
#pragma unroll 1
                for (int col = tid; col < SQ; col += 128) {
                    if (pass == 0) sts32(sb + OFF_M + col * 4, reduce_partials<true>(sb, col));
                    else sts32(sb + OFF_L + col * 4, 1.0f / reduce_partials<false>(sb, col));
                }
                nb_sync(NB_WG0, 128);
            }
            nb_arrive(NB_PF, 384);
        }
    } else {
        asm volatile("setmaxnreg.inc.sync.aligned.u32 176;");
        const uint32_t h = wg - 1;
        float o0[72], o1[72];
#pragma unroll
        for (int i = 0; i < 72; i++) { o0[i] = 0.f; o1[i] = 0.f; }
#pragma unroll 1
        for (int j = 0; j < NT - 1 - (int)h; j++) {
            const uint32_t par = j & 1;
            const uint64_t da = mkdesc(sb + OFF_V + (par * 2 + h) * HALF);
            const uint64_t db = mkdesc(sb + OFF_P + par * CH_Q);
            mbar_wait(sb + BAR_VF + par * 16 + h * 8, (j >> 1) & 1);
            nb_sync(NB_PF + h, 256);
            wg_fence();
#pragma unroll
            for (int kk = 0; kk < 4; kk++) {
                wgmma_acc<1>(o0, da + (uint64_t)((kk * 2048) >> 4), db + (uint64_t)((kk * 32) >> 4));
                wgmma_acc<1>(o1, da + (uint64_t)((8192 + kk * 2048) >> 4), db + (uint64_t)((kk * 32) >> 4));
            }
            wg_commit();
            if (tid == 0 && j + 2 < NT) mbar_expect(sb + BAR_VF + par * 16 + h * 8, HALF);
            wg_wait<0>();
            if (j + 2 < NT) {
                nb_arrive(NB_PE, 384);
                if (lane == 0) mbar_arrive_cta(sb + BAR_VE + par * 8, h);
            }
        }
        const uint64_t da = mkdesc(sb + OFF_V + h * HALF), db = mkdesc(sb + OFF_P);
        constexpr uint64_t DA1 = (2 * HALF) >> 4, DB1 = CH_Q >> 4, DC1 = 8192 >> 4;
        const uint32_t laddr = sb + OFF_L + (lane & 3) * 144;
        const uint32_t oaddr = sb + OFF_Q + h * 2 * CH_Q + st_off;
        float4 w[9];
        mbar_wait(sb + BAR_VF + 16 + h * 8, 1);
        if (h == 0) {
            nb_sync(NB_PA1, 256);
            issue_pv_lo(o0, da + DA1, db + DB1);
            issue_pv_lo(o1, da + DA1 + DC1, db + DB1);
            mbar_wait(sb + BAR_L, 0);
            float4 wa[9];
#pragma unroll
            for (int i = 0; i < 4; i++) wa[i] = lds128(laddr + i * 16);
            wg_wait<1>();
            reg_fence_part<0, 32>(o0);
            stage_out<0, 4>(o0, wa, oaddr);
            fence_async();
            nb_arrive(NB_EPI, 160);
            wg_wait<0>();
            reg_fence_part<0, 32>(o1);
            stage_out<0, 4>(o1, wa, oaddr + CH_Q);
#pragma unroll
            for (int i = 0; i < 32; i++) { asm volatile("" : "=f"(o0[i])); asm volatile("" : "=f"(o1[i])); }
            fence_async();
            nb_arrive(NB_EPI + 1, 160);
            nb_sync(NB_PB, 256);
        } else {
            mbar_wait(sb + BAR_VF + 8, 1);
            nb_sync(NB_PF + 1, 256);
            wg_fence();
            issue_pv(o0, da, db);
            wg_commit();
        }
        wg_fence();
        issue_pv(o0, da + DA1, db + DB1);
        wg_commit();
        mbar_wait(sb + BAR_L + 8, 0);
#pragma unroll
        for (int i = 4; i < 8; i++) w[i] = lds128(laddr + i * 16);
        wg_wait<0>();
        reg_fence(o0);
        stage_out<4, 5>(o0, w, oaddr);
        w[8] = lds128(laddr + 8 * 16);
        stage_out<5, 9>(o0, w, oaddr);
        fence_async();
        nb_arrive(NB_EPI + 4 * h + 2, 160);
        if (h) {
#pragma unroll
            for (int i = 0; i < 4; i++) w[i] = lds128(laddr + i * 16);
            stage_out<0, 4>(o0, w, oaddr);
            fence_async();
            nb_arrive(NB_EPI + 4, 160);
            wg_fence();
            issue_pv(o1, da + DC1, db);
            wg_commit();
        }
        wg_fence();
        issue_pv(o1, da + DA1 + DC1, db + DB1);
        wg_commit();
        if (h == 0) nb_arrive(NB_PF + 1, 256);
        wg_wait<0>();
        reg_fence(o1);
        stage_out<4, 9>(o1, w, oaddr + CH_Q);
        fence_async();
        nb_arrive(NB_EPI + 4 * h + 3, 160);
        if (h) {
            stage_out<0, 4>(o1, w, oaddr + CH_Q);
            fence_async();
            nb_arrive(NB_EPI + 5, 160);
        }
        if (needs_exact(sb)) {
            nb_sync(NB_FB, 448);
#pragma unroll
            for (int i = 0; i < 72; i++) { o0[i] = 0.f; o1[i] = 0.f; }
#pragma unroll 1
            for (int j = 0; j < NT; j++) {
                nb_sync(NB_PF, 384);
                mbar_wait(sb + BAR_FV, j & 1);
                wg_fence();
                issue_pv(o0, da, db);
                issue_pv(o1, da + DC1, db);
                wg_commit();
                wg_wait<0>();
                nb_sync(NB_PE, 384);
            }
            reg_fence(o0);
            reg_fence(o1);
            nb_sync(NB_PF, 384);
            exact_out<0>(o0, o1, oaddr, laddr);
            fence_async();
            nb_sync(NB_EPI + h, 128);
            if (warp == 0 && elect()) {
                for (int ch = 2 * h; ch < 2 * h + 2; ch++) {
                    tma_store(&mo_lo, sb + OFF_Q + ch * CH_Q, qrow, ch);
                    tma_store(&mo_hi, sb + OFF_Q + ch * CH_Q + 8192, qrow + 64, ch);
                }
                asm volatile("cp.async.bulk.commit_group;\ncp.async.bulk.wait_group.read 0;" ::: "memory");
            }
        }
    }
}

typedef CUresult (*EncodeFn)(CUtensorMap*, CUtensorMapDataType, cuuint32_t, void*, const cuuint64_t*, const cuuint64_t*,
                             const cuuint32_t*, const cuuint32_t*, CUtensorMapInterleave, CUtensorMapSwizzle,
                             CUtensorMapL2promotion, CUtensorMapFloatOOBfill);

CUtensorMap make_map(EncodeFn enc, void* ptr, uint64_t rows, uint32_t box_rows, uint32_t box_chunks) {
    CUtensorMap m;
    cuuint64_t dims[3] = {64, rows, 4};
    cuuint64_t strides[2] = {512, 128};
    cuuint32_t box[3] = {64, box_rows, box_chunks};
    cuuint32_t es[3] = {1, 1, 1};
    enc(&m, CU_TENSOR_MAP_DATA_TYPE_BFLOAT16, 3, ptr, dims, strides, box, es, CU_TENSOR_MAP_INTERLEAVE_NONE,
        CU_TENSOR_MAP_SWIZZLE_128B, CU_TENSOR_MAP_L2_PROMOTION_L2_128B, CU_TENSOR_MAP_FLOAT_OOB_FILL_NONE);
    return m;
}

}

extern "C" void kernel_launch(void* const* d_in, const int* in_sizes, int n_in, void* d_out, int out_size) {
    static EncodeFn enc = nullptr;
    static uint32_t pace = 256;
    if (!enc) {
        int dev = 0, sm_khz = 0, mem_khz = 0, bus_bits = 0;
        cudaGetDevice(&dev);
        cudaDeviceGetAttribute(&sm_khz, cudaDevAttrClockRate, dev);
        cudaDeviceGetAttribute(&mem_khz, cudaDevAttrMemoryClockRate, dev);
        cudaDeviceGetAttribute(&bus_bits, cudaDevAttrGlobalMemoryBusWidth, dev);
        if (sm_khz > 0 && mem_khz > 0 && bus_bits > 0) {
            const double r = 256.0 * (sm_khz / 1980000.0) * (2619000.0 * 5120.0) / ((double)mem_khz * bus_bits);
            pace = r < 512.0 ? (uint32_t)(r + 0.5) : 512u;
        }
        void* fn = nullptr;
        cudaDriverEntryPointQueryResult qr;
        cudaGetDriverEntryPoint("cuTensorMapEncodeTiled", &fn, cudaEnableDefault, &qr);
        enc = (EncodeFn)fn;
        cudaFuncSetAttribute(gqa_kernel, cudaFuncAttributeMaxDynamicSharedMemorySize, SMEM_BYTES);
    }
    const CUtensorMap mq = make_map(enc, d_in[0], 128 * SQ, SQ, 1);
    const CUtensorMap mk = make_map(enc, d_in[1], 64 * SK, 64, 2);
    const CUtensorMap mv = make_map(enc, d_in[2], 64 * SK, 64, 2);
    const CUtensorMap mo_lo = make_map(enc, d_out, 128 * SQ, 64, 1);
    const CUtensorMap mo_hi = make_map(enc, d_out, 128 * SQ, 80, 1);
    gqa_kernel<<<128, 512, SMEM_BYTES, cudaStreamPerThread>>>(mq, mk, mv, mo_lo, mo_hi, pace);
}
```
